```python
import torch

def _softmax(x, axis=-1):
    return torch.softmax(x, dim=axis)
def _gelu(x):
    return torch.nn.functional.gelu(x, approximate="tanh")
def _silu(x):
    return torch.nn.functional.silu(x)
def _sigmoid(x):
    return torch.sigmoid(x)
def _layernorm(x, axis=-1, eps=1e-5):
    m = x.mean(dim=axis, keepdim=True)
    v = x.var(dim=axis, keepdim=True, unbiased=False)
    return (x - m) / torch.sqrt(v + eps)
def _scatter_add(tgt, idx, src, axis=0):
    return tgt.clone().index_add_(axis, idx, src)
def _segment_sum(src, seg, n):
    out = torch.zeros((n,) + src.shape[1:], dtype=src.dtype)
    return out.index_add_(0, seg, src)
def _pad(x, pw):
    flat = tuple(v for pair in reversed(pw) for v in pair)
    return torch.nn.functional.pad(x, flat)

kernel_name = 'standalone__groupnorm__sampling'

def setup_inputs():

    _w = (lambda a: (lambda t: t.to(torch.bfloat16) if t.is_floating_point() else t)(torch.as_tensor(a)))
    B = 32
    G = 32
    cpg = max(1, 512 // G)
    C = G * cpg
    H, W = 32, 16
    return {
        "x": _w(abs((lambda *s: torch.randn(*s, dtype=torch.bfloat16) * 0.05)(B, C, H, W))),
        "g": _w((lambda *s: torch.randn(*s, dtype=torch.bfloat16) * 0.05)(C) + 1.0),
        "b": _w((lambda *s: torch.randn(*s, dtype=torch.bfloat16) * 0.4)(C)),
    }

def reference(x, g, b):
    G = 32
    B, C, H, W = x.shape[0], x.shape[1], x.shape[2], x.shape[3]
    xr = x.reshape(B, G, C // G, H, W)
    mu = xr.mean(axis=(2, 3, 4), keepdims=True)
    var = ((xr - mu) ** 2).mean(axis=(2, 3, 4), keepdims=True)
    xn = (xr - mu) / torch.sqrt(var + 1e-5)
    xn = xn.reshape(B, C, H, W)
    return xn * g[None, :, None, None] + b[None, :, None, None]
```

```cpp
#include <cuda_runtime.h>
#include <cuda_bf16.h>
#include <stdint.h>


constexpr int kGroupElems = 8192;
constexpr int kHW = 512;
constexpr int kCPG = 16;
constexpr int kG = 32;

__device__ __forceinline__ float bf_lo(uint32_t v) { return __uint_as_float(v << 16); }
__device__ __forceinline__ float bf_hi(uint32_t v) { return __uint_as_float(v & 0xffff0000u); }
__device__ __forceinline__ uint32_t pack_bf(float lo, float hi) {
    uint32_t r;
    asm("cvt.rn.bf16x2.f32 %0, %1, %2;" : "=r"(r) : "f"(hi), "f"(lo));
    return r;
}

template <int THREADS>
__global__ void __launch_bounds__(THREADS) gn_kernel(const uint4* __restrict__ x,
                                                      const __nv_bfloat16* __restrict__ g,
                                                      const __nv_bfloat16* __restrict__ b,
                                                      uint4* __restrict__ out) {
    constexpr int VEC = kGroupElems / 8 / THREADS;
    constexpr int WARPS = THREADS / 32;
    __shared__ float2 red[WARPS];
    const int grp = blockIdx.x;
    const int tid = threadIdx.x;
    const uint4* src = x + (size_t)grp * (kGroupElems / 8) + tid;
    uint4 v[VEC];
#pragma unroll
    for (int i = 0; i < VEC; i++) v[i] = __ldcs(src + i * THREADS);

    float s = 0.f;
#pragma unroll
    for (int i = 0; i < VEC; i++) {
        s += (bf_lo(v[i].x) + bf_hi(v[i].x)) + (bf_lo(v[i].y) + bf_hi(v[i].y)) +
             (bf_lo(v[i].z) + bf_hi(v[i].z)) + (bf_lo(v[i].w) + bf_hi(v[i].w));
    }
#pragma unroll
    for (int o = 16; o > 0; o >>= 1) s += __shfl_xor_sync(0xffffffffu, s, o);
    const float wmean = s * (1.0f / (VEC * 8 * 32));
    float q = 0.f;
#pragma unroll
    for (int i = 0; i < VEC; i++) {
        float d;
        d = bf_lo(v[i].x) - wmean; q = fmaf(d, d, q);
        d = bf_hi(v[i].x) - wmean; q = fmaf(d, d, q);
        d = bf_lo(v[i].y) - wmean; q = fmaf(d, d, q);
        d = bf_hi(v[i].y) - wmean; q = fmaf(d, d, q);
        d = bf_lo(v[i].z) - wmean; q = fmaf(d, d, q);
        d = bf_hi(v[i].z) - wmean; q = fmaf(d, d, q);
        d = bf_lo(v[i].w) - wmean; q = fmaf(d, d, q);
        d = bf_hi(v[i].w) - wmean; q = fmaf(d, d, q);
    }
#pragma unroll
    for (int o = 16; o > 0; o >>= 1) q += __shfl_xor_sync(0xffffffffu, q, o);
    if ((tid & 31) == 0) red[tid >> 5] = make_float2(wmean, q);
    __syncthreads();
    float mean = 0.f, m2 = 0.f;
#pragma unroll
    for (int w = 0; w < WARPS; w++) { mean += red[w].x; m2 += red[w].y; }
    mean *= (1.0f / WARPS);
    float dm = 0.f;
#pragma unroll
    for (int w = 0; w < WARPS; w++) { float d = red[w].x - mean; dm = fmaf(d, d, dm); }
    const float var = (m2 + dm * (float)(VEC * 8 * 32)) * (1.0f / kGroupElems);
    const float rstd = 1.0f / sqrtf(var + 1e-5f);

    const int c0 = (grp % kG) * kCPG;
    uint4* dst = out + (size_t)grp * (kGroupElems / 8) + tid;
#pragma unroll
    for (int i = 0; i < VEC; i++) {
        const int c = c0 + (i * THREADS + tid) / (kHW / 8);
        const float a = rstd * __bfloat162float(g[c]);
        const float sh = fmaf(-mean, a, __bfloat162float(b[c]));
        uint4 o;
        o.x = pack_bf(fmaf(bf_lo(v[i].x), a, sh), fmaf(bf_hi(v[i].x), a, sh));
        o.y = pack_bf(fmaf(bf_lo(v[i].y), a, sh), fmaf(bf_hi(v[i].y), a, sh));
        o.z = pack_bf(fmaf(bf_lo(v[i].z), a, sh), fmaf(bf_hi(v[i].z), a, sh));
        o.w = pack_bf(fmaf(bf_lo(v[i].w), a, sh), fmaf(bf_hi(v[i].w), a, sh));
        dst[i * THREADS] = o;
    }
}

extern "C" void kernel_launch(void* const* d_in, const int* in_sizes, int n_in,
                              void* d_out, int out_size) {
    const uint4* x = (const uint4*)d_in[0];
    const __nv_bfloat16* g = (const __nv_bfloat16*)d_in[1];
    const __nv_bfloat16* b = (const __nv_bfloat16*)d_in[2];
    const int ngroups = in_sizes[0] / kGroupElems;
    gn_kernel<256><<<ngroups, 256>>>(x, g, b, (uint4*)d_out);
}
```

```cpp
#include <cuda_runtime.h>
#include <cuda_bf16.h>
#include <stdint.h>


namespace {

constexpr int kGroupBytes = 16384;
constexpr int kThreads = 128;
constexpr int kVec = kGroupBytes / 16 / kThreads;
constexpr int kWarpElems = kVec * 8 * 32;
constexpr uint32_t kFirst = 40;
constexpr uint32_t kKnee = 300;
constexpr uint32_t kStep1 = 1300 * 31;
constexpr uint32_t kStep2 = 875 * 31;

__device__ __forceinline__ float bf_lo(uint32_t v) { return __uint_as_float(v << 16); }
__device__ __forceinline__ float bf_hi(uint32_t v) { return __uint_as_float(v & 0xffff0000u); }
__device__ __forceinline__ float bf_lo2(uint32_t v) { return __uint_as_float(__byte_perm(v, 0, 0x1044)); }
__device__ __forceinline__ float bf_hi2(uint32_t v) { return __uint_as_float(__byte_perm(v, 0, 0x3244)); }
__device__ __forceinline__ uint32_t pack_bf(float lo, float hi) {
    uint32_t r;
    asm("cvt.rn.bf16x2.f32 %0, %1, %2;" : "=r"(r) : "f"(hi), "f"(lo));
    return r;
}
__device__ __forceinline__ uint4 ld_stream(const void* p) {
    uint4 v;
    asm volatile("ld.global.cs.v4.u32 {%0,%1,%2,%3}, [%4];"
                 : "=r"(v.x), "=r"(v.y), "=r"(v.z), "=r"(v.w) : "l"(p) : "memory");
    return v;
}
__device__ __forceinline__ void st_vec(void* p, uint4 v) {
    asm volatile("st.volatile.global.v4.u32 [%0], {%1,%2,%3,%4};"
                 :: "l"(p), "r"(v.x), "r"(v.y), "r"(v.z), "r"(v.w) : "memory");
}
__device__ __forceinline__ uint32_t lds_word(uint32_t a) {
    uint32_t v;
    asm volatile("ld.volatile.shared.u32 %0, [%1];" : "=r"(v) : "r"(a) : "memory");
    return v;
}
__device__ __forceinline__ uint4 normalize8(const uint4& w, float a, float s) {
    uint4 o;
    o.x = pack_bf(fmaf(bf_lo2(w.x), a, s), fmaf(bf_hi2(w.x), a, s));
    o.y = pack_bf(fmaf(bf_lo2(w.y), a, s), fmaf(bf_hi2(w.y), a, s));
    o.z = pack_bf(fmaf(bf_lo2(w.z), a, s), fmaf(bf_hi2(w.z), a, s));
    o.w = pack_bf(fmaf(bf_lo2(w.w), a, s), fmaf(bf_hi2(w.w), a, s));
    return o;
}

__device__ __forceinline__ void fetch_params(uint32_t sa, uint32_t tid, uint32_t grp,
                                             const uint32_t* gamma, const uint32_t* beta) {
    if (tid >= kThreads - 4) {
        const uint32_t* p = ((tid & 2) ? beta : gamma) + (grp & 31) * 8 + (tid & 1) * 4;
        asm volatile("cp.async.ca.shared.global [%0], [%1], 16;"
                     :: "r"(sa + 32 + (tid & 3) * 16), "l"(p) : "memory");
    }
}

__global__ void __launch_bounds__(kThreads, 8)
groupnorm_kernel(const char* __restrict__ x, const uint32_t* __restrict__ gamma,
                 const uint32_t* __restrict__ beta, char* __restrict__ out) {
    __shared__ __align__(16) uint32_t sh[24];
    const uint32_t tid = threadIdx.x, grp = blockIdx.x;
    const uint32_t off = ((tid & 96u) << 7) + ((tid & 31u) << 4);
    const char* src = x + (size_t)grp * kGroupBytes + off;
    uint32_t sa = (uint32_t)__cvta_generic_to_shared(sh);
    asm volatile("" : "+r"(sa));
    uint4 v[kVec];
    if (grp < kFirst) {
#pragma unroll
        for (int k = 0; k < kVec; k++) v[k] = ld_stream(src + k * 512);
        fetch_params(sa, tid, grp, gamma, beta);
    } else {
        fetch_params(sa, tid, grp, gamma, beta);
        const uint32_t t0 = clock();
        const uint32_t d = (grp < kKnee ? (grp - kFirst) * kStep1
                                        : (kKnee - kFirst) * kStep1 + (grp - kKnee) * kStep2) >> 12;
        while ((uint32_t)clock() - t0 < d) __nanosleep(20);
#pragma unroll
        for (int k = 0; k < kVec; k++) v[k] = ld_stream(src + k * 512);
    }

    const float piv = bf_lo(__shfl_sync(0xffffffffu, v[0].x, 0));
    float s0 = 0.f, s1 = 0.f, q0 = 0.f, q1 = 0.f;
#pragma unroll
    for (int k = 0; k < kVec; k++) {
        float d;
        d = bf_lo(v[k].x) - piv; s0 += d; q0 = fmaf(d, d, q0);
        d = bf_hi(v[k].x) - piv; s1 += d; q1 = fmaf(d, d, q1);
        d = bf_lo(v[k].y) - piv; s0 += d; q0 = fmaf(d, d, q0);
        d = bf_hi(v[k].y) - piv; s1 += d; q1 = fmaf(d, d, q1);
        d = bf_lo(v[k].z) - piv; s0 += d; q0 = fmaf(d, d, q0);
        d = bf_hi(v[k].z) - piv; s1 += d; q1 = fmaf(d, d, q1);
        d = bf_lo(v[k].w) - piv; s0 += d; q0 = fmaf(d, d, q0);
        d = bf_hi(v[k].w) - piv; s1 += d; q1 = fmaf(d, d, q1);
    }
    float S = s0 + s1, SS = q0 + q1;
#pragma unroll
    for (int o = 16; o > 0; o >>= 1) {
        S += __shfl_xor_sync(0xffffffffu, S, o);
        SS += __shfl_xor_sync(0xffffffffu, SS, o);
    }
    if ((tid & 31) == 0) {
        const float m = S * (1.0f / kWarpElems);
        asm volatile("st.shared.v2.f32 [%0], {%1, %2};"
                     :: "r"(sa + (tid >> 2)), "f"(piv + m), "f"(fmaf(-m, S, SS)) : "memory");
    }
    asm volatile("cp.async.wait_all;" ::: "memory");
    __syncthreads();

    float4 r0, r1;
    asm volatile("ld.shared.v4.f32 {%0,%1,%2,%3}, [%4];"
                 : "=f"(r0.x), "=f"(r0.y), "=f"(r0.z), "=f"(r0.w) : "r"(sa) : "memory");
    asm volatile("ld.shared.v4.f32 {%0,%1,%2,%3}, [%4+16];"
                 : "=f"(r1.x), "=f"(r1.y), "=f"(r1.z), "=f"(r1.w) : "r"(sa) : "memory");
    const uint32_t pa = sa + 32 + ((tid & 96u) >> 2);
    uint32_t gw = lds_word(pa), bw = lds_word(pa + 32);
    const float mean = ((r0.x + r0.z) + (r1.x + r1.z)) * 0.25f;
    const float d0 = r0.x - mean, d1 = r0.z - mean, d2 = r1.x - mean, d3 = r1.z - mean;
    const float within = fmaf((r0.y + r0.w) + (r1.y + r1.w), 1.0f / 8192, 1e-5f);
    const float var_eps = fmaf(fmaf(d0, d0, d1 * d1) + fmaf(d2, d2, d3 * d3), 0.25f, within);
    float rstd;
    asm("rsqrt.approx.ftz.f32 %0, %1;" : "=f"(rstd) : "f"(var_eps));

    char* dst = out + (size_t)grp * kGroupBytes + off;
#pragma unroll
    for (int c = 0; c < 4; c++) {
        const float a = rstd * ((c & 1) ? bf_hi2(gw) : bf_lo2(gw));
        const float s = fmaf(-mean, a, (c & 1) ? bf_hi2(bw) : bf_lo2(bw));
        st_vec(dst + (2 * c) * 512, normalize8(v[2 * c], a, s));
        st_vec(dst + (2 * c + 1) * 512, normalize8(v[2 * c + 1], a, s));
        if (c < 3) {
            gw = lds_word(pa + ((c + 1) >> 1) * 4);
            bw = lds_word(pa + 32 + ((c + 1) >> 1) * 4);
        }
    }
}

}

extern "C" void kernel_launch(void* const* d_in, const int* in_sizes, int n_in,
                              void* d_out, int out_size) {
    const int ngroups = in_sizes[0] / (kGroupBytes / 2);
    groupnorm_kernel<<<ngroups, kThreads>>>((const char*)d_in[0], (const uint32_t*)d_in[1],
                                            (const uint32_t*)d_in[2], (char*)d_out);
}
```
